```python
import torch

def _softmax(x, axis=-1):
    return torch.softmax(x, dim=axis)
def _gelu(x):
    return torch.nn.functional.gelu(x, approximate="tanh")
def _silu(x):
    return torch.nn.functional.silu(x)
def _sigmoid(x):
    return torch.sigmoid(x)
def _layernorm(x, axis=-1, eps=1e-5):
    m = x.mean(dim=axis, keepdim=True)
    v = x.var(dim=axis, keepdim=True, unbiased=False)
    return (x - m) / torch.sqrt(v + eps)
def _scatter_add(tgt, idx, src, axis=0):
    return tgt.clone().index_add_(axis, idx, src)
def _segment_sum(src, seg, n):
    out = torch.zeros((n,) + src.shape[1:], dtype=src.dtype)
    return out.index_add_(0, seg, src)
def _pad(x, pw):
    flat = tuple(v for pair in reversed(pw) for v in pair)
    return torch.nn.functional.pad(x, flat)

kernel_name = 'gated_mix__mha_block__ssm_conv_s4__prompt'

def setup_inputs():

    _w = (lambda a: (lambda t: t.to(torch.bfloat16) if t.is_floating_point() else t)(torch.as_tensor(a)))
    def _A_setup():
        B, S, D, H = 1, 2048, 576, 32
        return {
            "x": _w((lambda *s: torch.randn(*s, dtype=torch.bfloat16) * 0.05)(B, S, D)),
            "wqkv": _w((lambda *s: torch.randn(*s, dtype=torch.bfloat16) * 0.8)(D, 3 * D)),
            "wo": _w((lambda *s: torch.randn(*s, dtype=torch.bfloat16) * 0.05)(D, D)),
        }
    _A_in = _A_setup()

    def _B_setup():
        B, L, D, N = 1, 2048, 576, 128
        A_re = -(lambda _x: torch.exp(torch.as_tensor(_x)))((lambda *s: torch.randn(*s, dtype=torch.bfloat16) * 6.4)(D, N))
        A_im = torch.pi * (lambda *s: torch.randn(*s, dtype=torch.bfloat16) * 0.1)(D, N)
        B_re = (lambda *s: torch.randn(*s, dtype=torch.bfloat16) * 0.2)(D, N)
        B_im = (lambda *s: torch.randn(*s, dtype=torch.bfloat16) * 0.2)(D, N)
        C_re = (lambda *s: torch.randn(*s, dtype=torch.bfloat16) * 0.2)(D, N)
        C_im = (lambda *s: torch.randn(*s, dtype=torch.bfloat16) * 0.2)(D, N)
        log_dt = (lambda *s: torch.randn(*s, dtype=torch.bfloat16) * 0.1)(D) * 0.5 - 4.0
        Dskip = (lambda *s: torch.randn(*s, dtype=torch.bfloat16) * 0.1)(D)
        return {
            "u": _w((lambda *s: torch.randn(*s, dtype=torch.bfloat16) * 0.05)(B, L, D)),
            "A_re": _w(A_re),
            "A_im": _w(A_im),
            "B_re": _w(B_re),
            "B_im": _w(B_im),
            "C_re": _w(C_re),
            "C_im": _w(C_im),
            "log_dt": _w(log_dt),
            "Dskip": _w(Dskip),
        }
    _B_in = _B_setup()

    return {
        "A_x": _A_in["x"],
        "A_wqkv": _A_in["wqkv"],
        "A_wo": _A_in["wo"],
        "B_u": _B_in["u"],
        "B_A_re": _B_in["A_re"],
        "B_A_im": _B_in["A_im"],
        "B_B_re": _B_in["B_re"],
        "B_B_im": _B_in["B_im"],
        "B_C_re": _B_in["C_re"],
        "B_C_im": _B_in["C_im"],
        "B_log_dt": _B_in["log_dt"],
        "B_Dskip": _B_in["Dskip"],
        "gate_w": _w((lambda *s: torch.randn(*s, dtype=torch.bfloat16) * 0.05)(576) * 16.0),
    }

def reference(A_x, A_wqkv, A_wo, B_u, B_A_re, B_A_im, B_B_re, B_B_im, B_C_re, B_C_im, B_log_dt, B_Dskip, gate_w):
    def _A_ref(x, wqkv, wo):
        B, S, D = x.shape
        H = 32
        Dh = D // H
        qkv = (lambda x, *d: x.permute(*d))((x @ wqkv).reshape(B, S, 3, H, Dh), 2, 0, 3, 1, 4)
        q, k, v = qkv[0], qkv[1], qkv[2]
        scores = torch.einsum("bhqd,bhkd->bhqk", q, k) * (Dh ** -0.5)
        p = _softmax(scores, axis=-1)
        o = torch.einsum("bhqk,bhkd->bhqd", p, v)
        return (lambda x, *d: x.permute(*d))(o, 0, 2, 1, 3).reshape(B, S, D) @ wo

    def _B_ref(u, A_re, A_im, B_re, B_im, C_re, C_im, log_dt, Dskip):
        Bsz, L, D = u.shape
        dt = torch.exp(log_dt)[:, None]
        A = A_re + 1j * A_im
        Bc = B_re + 1j * B_im
        Cc = C_re + 1j * C_im
        logdA = dt * A
        dB = dt * Bc
        l = (lambda x, dt: x.to(dt))(torch.arange(L), A_re.dtype)
        P = torch.exp(logdA[:, :, None] * l[None, None, :])
        K = torch.einsum("dn,dnl,dn->dl", Cc, P, dB).real
        L2 = 2 * L
        Kp = _pad(K, ((0, 0), (0, L)))
        up = (lambda x, *d: x.permute(*d))(u, 0, 2, 1)
        up = _pad(up, ((0, 0), (0, 0), (0, L)))
        Kf = (lambda x, axes=(-2,-1): torch.fft.rfft2(x.float(), dim=axes))(Kp[:, None, :], axes=(-2, -1))
        Uf = (lambda x, axes=(-2,-1): torch.fft.rfft2(x.float(), dim=axes))(up[:, :, None, :], axes=(-2, -1))
        Yf = Uf * Kf[None, :, :, :]
        y = (lambda x, s, axes=(-2,-1): torch.fft.irfft2(x, s=s, dim=axes).to(torch.bfloat16))(Yf, (1, L2), axes=(-2, -1))[:, :, 0, :L]
        y = (lambda x, *d: x.permute(*d))(y, 0, 2, 1) + u * Dskip[None, None, :]
        return y

    x = A_x
    g = _sigmoid((x * gate_w).sum(-1, keepdims=True))
    a = _A_ref(x, A_wqkv, A_wo)
    b = _B_ref(x, B_A_re, B_A_im, B_B_re, B_B_im, B_C_re, B_C_im, B_log_dt, B_Dskip)
    return g * a + (1 - g) * b
```

```cpp
#include <cuda_runtime.h>
#include <cuda_bf16.h>
#include <cuda_fp16.h>
#include <cuda.h>
#include <stdint.h>

namespace {

constexpr int S_ = 2048, D_ = 576, H_ = 32, DH = 18, NST = 128;
constexpr int GROUP_B = 384;
constexpr int HEAD_B = 256 * GROUP_B;
constexpr int KT_B = 16 * GROUP_B;

constexpr int KV_FIRST = 3;
__host__ __device__ constexpr bool is_mufu(int jj) { return (0x92 >> (jj & 7)) & 1; }

constexpr float QSCALE = 0.23570226039551584f * 1.4426950408889634f;

__device__ __align__(1024) uint16_t g_Qp[H_ * 256 * 192];
__device__ __align__(1024) uint16_t g_KV[H_ * 16 * 2 * 3072];
__device__ float g_kmax2[16 * H_];
__device__ uint32_t g_vmax[16 * H_];
__device__ __align__(1024) __nv_bfloat16 g_O[S_ * D_];
__device__ __align__(1024) __nv_bfloat16 g_bT[D_ * S_];
__device__ __align__(1024) uint4 g_WoT[4 * 72 * 18 * 8];
__device__ uint32_t g_cnt[33];
__device__ uint32_t g_gate[S_];

__device__ __forceinline__ uint32_t smem_u32(const void* p) { return (uint32_t)__cvta_generic_to_shared(p); }
__device__ __forceinline__ void mbar_init(uint32_t bar, uint32_t cnt) { asm volatile("mbarrier.init.shared::cta.b64 [%0], %1;" ::"r"(bar), "r"(cnt)); }
__device__ __forceinline__ void mbar_expect_tx(uint32_t bar, uint32_t bytes) { asm volatile("mbarrier.arrive.expect_tx.shared::cta.b64 _, [%0], %1;" ::"r"(bar), "r"(bytes) : "memory"); }
__device__ __forceinline__ void mbar_arrive(uint32_t bar) { asm volatile("mbarrier.arrive.shared::cta.b64 _, [%0];" ::"r"(bar) : "memory"); }
__device__ __forceinline__ void mbar_wait(uint32_t bar, uint32_t parity) {
    asm volatile("{\n.reg .pred p;\nLAB_WAIT%=:\nmbarrier.try_wait.parity.shared::cta.b64 p, [%0], %1;\n@p bra DONE%=;\nbra LAB_WAIT%=;\nDONE%=:\n}" ::"r"(bar), "r"(parity) : "memory");
}
__device__ __forceinline__ void bulk_g2s(uint32_t dst, const void* src, uint32_t bytes, uint32_t bar) {
    asm volatile("cp.async.bulk.shared::cluster.global.mbarrier::complete_tx::bytes [%0], [%1], %2, [%3];" ::"r"(dst), "l"(src), "r"(bytes), "r"(bar) : "memory");
}
__device__ __forceinline__ void wg_fence() { asm volatile("wgmma.fence.sync.aligned;" ::: "memory"); }
__device__ __forceinline__ void wg_commit() { asm volatile("wgmma.commit_group.sync.aligned;" ::: "memory"); }
template <int N> __device__ __forceinline__ void wg_wait() { asm volatile("wgmma.wait_group.sync.aligned %0;" ::"n"(N) : "memory"); }
template <int N> __device__ __forceinline__ void reg_fence(float (&d)[N]) {
#pragma unroll
    for (int i = 0; i < N; i++) asm volatile("" : "+f"(d[i])::"memory");
}
template <int N> __device__ __forceinline__ void reg_fence_u(uint32_t (&d)[N]) {
#pragma unroll
    for (int i = 0; i < N; i++) asm volatile("" : "+r"(d[i])::"memory");
}
__device__ __forceinline__ uint64_t mkdesc(uint32_t addr, uint32_t lbo, uint32_t sbo) {
    return (uint64_t)((addr & 0x3FFFF) >> 4) | ((uint64_t)(lbo >> 4) << 16) | ((uint64_t)(sbo >> 4) << 32);
}
__device__ __forceinline__ void desc_bump(uint64_t& d, uint32_t inc) {
    asm("{.reg .b32 lo, hi; mov.b64 {lo, hi}, %0; add.u32 lo, lo, %1; mov.b64 %0, {lo, hi};}" : "+l"(d) : "r"(inc));
}
__device__ __forceinline__ void pdl_launch_dependents() { asm volatile("griddepcontrol.launch_dependents;" ::: "memory"); }
__device__ __forceinline__ void pdl_wait() { asm volatile("griddepcontrol.wait;" ::: "memory"); }
__device__ __forceinline__ void named_sync(int id, int n) { asm volatile("bar.sync %0, %1;" ::"r"(id), "r"(n) : "memory"); }
__device__ __forceinline__ void named_arrive(int id, int n) { asm volatile("bar.arrive %0, %1;" ::"r"(id), "r"(n) : "memory"); }
__device__ __forceinline__ float ex2f(float x) { float y; asm("ex2.approx.ftz.f32 %0, %1;" : "=f"(y) : "f"(x)); return y; }
__device__ __forceinline__ uint32_t pack_f16(float lo, float hi) { uint32_t r; asm("cvt.rn.f16x2.f32 %0, %1, %2;" : "=r"(r) : "f"(hi), "f"(lo)); return r; }
__device__ __forceinline__ uint32_t pack_bf16(float lo, float hi) { uint32_t r; asm("cvt.rn.bf16x2.f32 %0, %1, %2;" : "=r"(r) : "f"(hi), "f"(lo)); return r; }
__device__ __forceinline__ float shfl_idx_f(float v, int src) {
    float r; asm volatile("shfl.sync.idx.b32 %0, %1, %2, 0x1f, 0xffffffff;" : "=f"(r) : "f"(v), "r"(src)); return r;
}
__device__ __forceinline__ float bf_lo(uint32_t v) { return __uint_as_float(v << 16); }
__device__ __forceinline__ float bf_hi(uint32_t v) { return __uint_as_float(v & 0xFFFF0000u); }


__device__ __forceinline__ void tma_2d(uint32_t dst, const CUtensorMap* tm, int x, int y, uint32_t bar) {
    asm volatile("cp.async.bulk.tensor.2d.shared::cluster.global.mbarrier::complete_tx::bytes [%0], [%1, {%3, %4}], [%2];"
                 ::"r"(dst), "l"(tm), "r"(bar), "r"(x), "r"(y) : "memory");
}
__device__ __forceinline__ void bulk_s2g(void* dst, uint32_t src, uint32_t bytes) {
    asm volatile("cp.async.bulk.global.shared::cta.bulk_group [%0], [%1], %2;" ::"l"(dst), "r"(src), "r"(bytes) : "memory");
}
__device__ __forceinline__ void bulk_commit() { asm volatile("cp.async.bulk.commit_group;" ::: "memory"); }
__device__ __forceinline__ void bulk_wait0() { asm volatile("cp.async.bulk.wait_group 0;" ::: "memory"); }
__device__ __forceinline__ void fence_async_smem() { asm volatile("fence.proxy.async.shared::cta;" ::: "memory"); }
__device__ __forceinline__ uint64_t mkdesc_sw128(uint32_t addr, uint32_t lbo, uint32_t sbo) { return mkdesc(addr, lbo, sbo) | (1ull << 62); }
__device__ __forceinline__ void ldsm_x4(uint32_t& r0, uint32_t& r1, uint32_t& r2, uint32_t& r3, uint32_t addr) {
    asm volatile("ldmatrix.sync.aligned.m8n8.x4.shared.b16 {%0, %1, %2, %3}, [%4];" : "=r"(r0), "=r"(r1), "=r"(r2), "=r"(r3) : "r"(addr) : "memory");
}
__device__ __forceinline__ void ldsm_x2(uint32_t& r0, uint32_t& r1, uint32_t addr) {
    asm volatile("ldmatrix.sync.aligned.m8n8.x2.shared.b16 {%0, %1}, [%2];" : "=r"(r0), "=r"(r1) : "r"(addr) : "memory");
}
__device__ __forceinline__ void mma_bf16(float (&d)[4], uint32_t a0, uint32_t a1, uint32_t a2, uint32_t a3, uint32_t b0, uint32_t b1) {
    asm("mma.sync.aligned.m16n8k16.row.col.f32.bf16.bf16.f32 {%0, %1, %2, %3}, {%4, %5, %6, %7}, {%8, %9}, {%0, %1, %2, %3};"
        : "+f"(d[0]), "+f"(d[1]), "+f"(d[2]), "+f"(d[3]) : "r"(a0), "r"(a1), "r"(a2), "r"(a3), "r"(b0), "r"(b1));
}
__device__ __forceinline__ uint32_t lds32v(uint32_t addr) { uint32_t v; asm volatile("ld.volatile.shared.b32 %0, [%1];" : "=r"(v) : "r"(addr) : "memory"); return v; }
__device__ __forceinline__ void sts32(uint32_t addr, uint32_t v) { asm volatile("st.shared.b32 [%0], %1;" ::"r"(addr), "r"(v) : "memory"); }

__device__ __forceinline__ void wgmma_pv_n24(float (&d)[12], uint32_t a0, uint32_t a1, uint32_t a2, uint32_t a3, uint64_t descB, int scaleD) {
    asm volatile("{\n.reg .pred p;\nsetp.ne.b32 p, %17, 0;\n"
        "wgmma.mma_async.sync.aligned.m64n24k16.f32.f16.f16 "
        "{%0, %1, %2, %3, %4, %5, %6, %7, %8, %9, %10, %11}, "
        "{%12, %13, %14, %15}, %16, p, 1, 1, 1;\n}\n"
        : "+f"(d[0]), "+f"(d[1]), "+f"(d[2]), "+f"(d[3]), "+f"(d[4]), "+f"(d[5]), "+f"(d[6]), "+f"(d[7]), "+f"(d[8]),
          "+f"(d[9]), "+f"(d[10]), "+f"(d[11])
        : "r"(a0), "r"(a1), "r"(a2), "r"(a3), "l"(descB), "r"(scaleD));
}
__device__ __forceinline__ void wgmma_qk_n64(float (&d)[32], uint32_t a0, uint32_t a1, uint32_t a2, uint32_t a3, uint64_t descB, int scaleD) {
    asm volatile("{\n.reg .pred p;\nsetp.ne.b32 p, %37, 0;\n"
        "wgmma.mma_async.sync.aligned.m64n64k16.f32.bf16.bf16 "
        "{%0, %1, %2, %3, %4, %5, %6, %7, %8, %9, %10, %11, %12, %13, %14, %15, %16, %17, %18, %19, %20, %21, %22, %23,  "
        "%24, %25, %26, %27, %28, %29, %30, %31}, "
        "{%32, %33, %34, %35}, %36, p, 1, 1, 0;\n}\n"
        : "+f"(d[0]), "+f"(d[1]), "+f"(d[2]), "+f"(d[3]), "+f"(d[4]), "+f"(d[5]), "+f"(d[6]), "+f"(d[7]), "+f"(d[8]),
          "+f"(d[9]), "+f"(d[10]), "+f"(d[11]), "+f"(d[12]), "+f"(d[13]), "+f"(d[14]), "+f"(d[15]), "+f"(d[16]),
          "+f"(d[17]), "+f"(d[18]), "+f"(d[19]), "+f"(d[20]), "+f"(d[21]), "+f"(d[22]), "+f"(d[23]), "+f"(d[24]),
          "+f"(d[25]), "+f"(d[26]), "+f"(d[27]), "+f"(d[28]), "+f"(d[29]), "+f"(d[30]), "+f"(d[31])
        : "r"(a0), "r"(a1), "r"(a2), "r"(a3), "l"(descB), "r"(scaleD));
}
__device__ __forceinline__ void wgmma_ss_n216_tb(float (&d)[108], uint64_t descA, uint64_t descB, int scaleD) {
    asm volatile("{\n.reg .pred p;\nsetp.ne.b32 p, %110, 0;\n"
        "wgmma.mma_async.sync.aligned.m64n216k16.f32.bf16.bf16 "
        "{%0, %1, %2, %3, %4, %5, %6, %7, %8, %9, %10, %11, %12, %13, %14, %15, %16, %17, %18, %19, %20, %21, %22, %23,  "
        "%24, %25, %26, %27, %28, %29, %30, %31, %32, %33, %34, %35, %36, %37, %38, %39, %40, %41, %42, %43, %44, %45,  "
        "%46, %47, %48, %49, %50, %51, %52, %53, %54, %55, %56, %57, %58, %59, %60, %61, %62, %63, %64, %65, %66, %67,  "
        "%68, %69, %70, %71, %72, %73, %74, %75, %76, %77, %78, %79, %80, %81, %82, %83, %84, %85, %86, %87, %88, %89,  "
        "%90, %91, %92, %93, %94, %95, %96, %97, %98, %99, %100, %101, %102, %103, %104, %105, %106, %107}, "
        "%108, %109, p, 1, 1, 0, 1;\n}\n"
        : "+f"(d[0]), "+f"(d[1]), "+f"(d[2]), "+f"(d[3]), "+f"(d[4]), "+f"(d[5]), "+f"(d[6]), "+f"(d[7]), "+f"(d[8]),
          "+f"(d[9]), "+f"(d[10]), "+f"(d[11]), "+f"(d[12]), "+f"(d[13]), "+f"(d[14]), "+f"(d[15]), "+f"(d[16]),
          "+f"(d[17]), "+f"(d[18]), "+f"(d[19]), "+f"(d[20]), "+f"(d[21]), "+f"(d[22]), "+f"(d[23]), "+f"(d[24]),
          "+f"(d[25]), "+f"(d[26]), "+f"(d[27]), "+f"(d[28]), "+f"(d[29]), "+f"(d[30]), "+f"(d[31]), "+f"(d[32]),
          "+f"(d[33]), "+f"(d[34]), "+f"(d[35]), "+f"(d[36]), "+f"(d[37]), "+f"(d[38]), "+f"(d[39]), "+f"(d[40]),
          "+f"(d[41]), "+f"(d[42]), "+f"(d[43]), "+f"(d[44]), "+f"(d[45]), "+f"(d[46]), "+f"(d[47]), "+f"(d[48]),
          "+f"(d[49]), "+f"(d[50]), "+f"(d[51]), "+f"(d[52]), "+f"(d[53]), "+f"(d[54]), "+f"(d[55]), "+f"(d[56]),
          "+f"(d[57]), "+f"(d[58]), "+f"(d[59]), "+f"(d[60]), "+f"(d[61]), "+f"(d[62]), "+f"(d[63]), "+f"(d[64]),
          "+f"(d[65]), "+f"(d[66]), "+f"(d[67]), "+f"(d[68]), "+f"(d[69]), "+f"(d[70]), "+f"(d[71]), "+f"(d[72]),
          "+f"(d[73]), "+f"(d[74]), "+f"(d[75]), "+f"(d[76]), "+f"(d[77]), "+f"(d[78]), "+f"(d[79]), "+f"(d[80]),
          "+f"(d[81]), "+f"(d[82]), "+f"(d[83]), "+f"(d[84]), "+f"(d[85]), "+f"(d[86]), "+f"(d[87]), "+f"(d[88]),
          "+f"(d[89]), "+f"(d[90]), "+f"(d[91]), "+f"(d[92]), "+f"(d[93]), "+f"(d[94]), "+f"(d[95]), "+f"(d[96]),
          "+f"(d[97]), "+f"(d[98]), "+f"(d[99]), "+f"(d[100]), "+f"(d[101]), "+f"(d[102]), "+f"(d[103]), "+f"(d[104]),
          "+f"(d[105]), "+f"(d[106]), "+f"(d[107])
        : "l"(descA), "l"(descB), "r"(scaleD));
}
__device__ __forceinline__ void wgmma_ss_n72_tb(float (&d)[36], uint64_t descA, uint64_t descB, int scaleD) {
    asm volatile("{\n.reg .pred p;\nsetp.ne.b32 p, %38, 0;\n"
        "wgmma.mma_async.sync.aligned.m64n72k16.f32.bf16.bf16 "
        "{%0, %1, %2, %3, %4, %5, %6, %7, %8, %9, %10, %11, %12, %13, %14, %15, %16, %17, %18, %19, %20, %21, %22, %23,  "
        "%24, %25, %26, %27, %28, %29, %30, %31, %32, %33, %34, %35}, "
        "%36, %37, p, 1, 1, 0, 1;\n}\n"
        : "+f"(d[0]), "+f"(d[1]), "+f"(d[2]), "+f"(d[3]), "+f"(d[4]), "+f"(d[5]), "+f"(d[6]), "+f"(d[7]), "+f"(d[8]),
          "+f"(d[9]), "+f"(d[10]), "+f"(d[11]), "+f"(d[12]), "+f"(d[13]), "+f"(d[14]), "+f"(d[15]), "+f"(d[16]),
          "+f"(d[17]), "+f"(d[18]), "+f"(d[19]), "+f"(d[20]), "+f"(d[21]), "+f"(d[22]), "+f"(d[23]), "+f"(d[24]),
          "+f"(d[25]), "+f"(d[26]), "+f"(d[27]), "+f"(d[28]), "+f"(d[29]), "+f"(d[30]), "+f"(d[31]), "+f"(d[32]),
          "+f"(d[33]), "+f"(d[34]), "+f"(d[35])
        : "l"(descA), "l"(descB), "r"(scaleD));
}


template <bool CLAMP> __device__ __forceinline__ uint32_t exp2_pair_poly(float t0, float t1, uint32_t kOne, uint32_t kTop) {
    uint32_t L, M, P;
    asm("prmt.b32 %0, %1, %2, 0x5410;" : "=r"(L) : "r"(__float_as_uint(t0)), "r"(__float_as_uint(t1)));
    if (CLAMP) asm("max.s16x2 %0, %0, %1;" : "+r"(L) : "r"(0u));
    asm("lop3.b32 %0, %1, 0x03FF03FF, %2, 0xEA;" : "=r"(M) : "r"(L), "r"(kOne));
    asm("fma.rn.f16x2 %0, %1, %2, %3;" : "=r"(P) : "r"(M), "r"(kTop), "r"(0xa2cba2cbu));
    asm("fma.rn.f16x2 %0, %0, %0, %1;" : "+r"(P) : "r"(0x39723972u));
    asm("lop3.b32 %0, %1, 0x03FF03FF, %2, 0xB8;" : "=r"(M) : "r"(L), "r"(P));
    return M;
}

constexpr int CV_STAGE = 0;
constexpr int CV_KE = 0, CV_KO = 4128 + 32;
constexpr int CV_D = 8320;
constexpr int CV_U = CV_D + 1296;
constexpr int CV_WARP_B = (CV_U + 136 * 32 + 127) / 128 * 128;
static_assert(CV_KO + 4128 <= CV_D && 56 * 144 <= CV_D && CV_WARP_B % 16 == 0, "conv smem layout");

struct cplx { float x, y; };
__device__ __forceinline__ cplx cmul(cplx a, cplx b) { return {a.x * b.x - a.y * b.y, a.x * b.y + a.y * b.x}; }
__device__ __forceinline__ cplx csq(cplx a) { return {a.x * a.x - a.y * a.y, 2.f * a.x * a.y}; }
__device__ __forceinline__ cplx cexp_l(float zr2, float zi, float l) {
    const float e = ex2f(zr2 * l), th = zi * l;
    return {e * __cosf(th), e * __sinf(th)};
}

struct ConvParams {
    const __nv_bfloat16 *x, *Are, *Aim, *Bre, *Bim, *Cre, *Cim, *logdt, *Dskip;
};

__device__ __forceinline__ void conv_kgen_chunk(float (&acc)[2][3][4], float dt, uint32_t pa, uint32_t pb, uint32_t pc, uint32_t ws, int lane) {
    {
        const float zr2 = dt * bf_lo(pa) * 1.4426950408889634f, zi = dt * bf_hi(pa);
        const cplx cb = cmul({bf_lo(pc), bf_hi(pc)}, {dt * bf_lo(pb), dt * bf_hi(pb)});
        const uint32_t xs = ws + CV_STAGE + lane * 4, ys = xs + 32 * 144;
        auto putY = [&](int y, cplx v) { sts32(ys + y * 144, pack_bf16(v.x, -v.y)); };
        const cplx w1 = cexp_l(zr2, zi, 1.f), w8 = cexp_l(zr2, zi, 8.f), w256 = cexp_l(zr2, zi, 256.f), w32 = cexp_l(zr2, zi, 32.f);
        const cplx w2 = csq(w1), w3 = cmul(w2, w1), w4 = csq(w2), w6 = cmul(w4, w2);
        putY(0, {1.f, 0.f}); putY(1, w1); putY(2, w2); putY(3, w3); putY(4, w4); putY(5, cmul(w4, w1)); putY(6, w6); putY(7, cmul(w4, w3));
        putY(8, w256); putY(9, cmul(w256, w2)); putY(10, cmul(w256, w4)); putY(11, cmul(w256, w6));
        const cplx w512 = csq(w256), w768 = cmul(w512, w256), w1024 = csq(w512);
        putY(12, w512); putY(13, cmul(w512, w4)); putY(14, w768); putY(15, cmul(w768, w4));
        putY(16, w1024); putY(17, cmul(w1024, w256)); putY(18, cmul(w1024, w512)); putY(19, cmul(w1024, w768));
        putY(20, csq(w1024)); putY(21, {0.f, 0.f}); putY(22, {0.f, 0.f}); putY(23, {0.f, 0.f});
        const cplx w16 = csq(w8);
        cplx b0 = cb, b1 = cmul(cb, w8), b2 = cmul(cb, w16), b3 = cmul(b1, w16);
#pragma unroll 1
        for (int a1 = 0; a1 < 8; a1++) {
            const uint32_t xa = xs + a1 * 4 * 144;
            sts32(xa, pack_bf16(b0.x, b0.y)); sts32(xa + 144, pack_bf16(b1.x, b1.y));
            sts32(xa + 288, pack_bf16(b2.x, b2.y)); sts32(xa + 432, pack_bf16(b3.x, b3.y));
            b0 = cmul(b0, w32); b1 = cmul(b1, w32); b2 = cmul(b2, w32); b3 = cmul(b3, w32);
        }
        __syncwarp();
        const uint32_t aaddr = ws + CV_STAGE + ((lane & 7) + 8 * ((lane >> 3) & 1)) * 144 + (lane >> 4) * 16;
        const uint32_t baddr = ws + CV_STAGE + (32 + (lane & 7) + 8 * (lane >> 4)) * 144 + ((lane >> 3) & 1) * 16;
#pragma unroll 1
        for (int ks = 0; ks < 4; ks++) {
            uint32_t a[2][4], b[3][2];
            ldsm_x4(a[0][0], a[0][1], a[0][2], a[0][3], aaddr + ks * 32);
            ldsm_x4(a[1][0], a[1][1], a[1][2], a[1][3], aaddr + 16 * 144 + ks * 32);
            ldsm_x4(b[0][0], b[0][1], b[1][0], b[1][1], baddr + ks * 32);
            ldsm_x2(b[2][0], b[2][1], baddr + 16 * 144 + ks * 32);
#pragma unroll
            for (int m = 0; m < 2; m++)
#pragma unroll
                for (int n = 0; n < 3; n++) mma_bf16(acc[m][n], a[m][0], a[m][1], a[m][2], a[m][3], b[n][0], b[n][1]);
        }
        __syncwarp();
    }
}
__device__ __forceinline__ void conv_kgen_finish(const float (&acc)[2][3][4], float dsk, uint32_t ws, uint8_t* wsp, int lane) {
    const int g = lane >> 2, c = lane & 3;
    uint16_t* D = (uint16_t*)(wsp + CV_D);
#pragma unroll
    for (int m = 0; m < 2; m++)
#pragma unroll
        for (int n = 0; n < 3; n++)
#pragma unroll
            for (int e = 0; e < 4; e++) {
                const int a = 16 * m + g + 8 * (e >> 1), y = 8 * n + 2 * c + (e & 1);
                int idx;
                if (n == 0) idx = 8 * a + y;
                else if (n == 1) idx = y < 12 ? 256 + 4 * a + (y - 8) : 384 + 64 * ((y - 12) >> 1) + 2 * a + (y & 1);
                else idx = y < 20 ? 512 + 32 * (y - 16) + a : ((y == 20 && a == 0) ? 640 : 641);
                float v = acc[m][n][e];
                if (idx == 0) v += dsk;
                D[idx] = __bfloat16_as_ushort(__float2bfloat16(v));
            }
    __syncwarp();
#pragma unroll 1
    for (int G = lane; G < 258; G += 32) {
        uint32_t v[8];
#pragma unroll
        for (int e = 0; e < 8; e += 2) {
            const int l0 = 8 * G - 15 + e;
            const uint32_t bits = pack_bf16((float)l0, (float)(l0 + 1));
            const int i0 = l0 < 128 ? l0 : (int)(bits & 0xFFFFu) - 0x4280, i1 = l0 + 1 < 128 ? l0 + 1 : (int)(bits >> 16) - 0x4280;
            v[e] = (l0 >= 0 && l0 < S_) ? D[i0] : 0u;
            v[e + 1] = (l0 + 1 >= 0 && l0 + 1 < S_) ? D[i1] : 0u;
        }
        *(uint4*)(wsp + CV_KE + 16 * G) = make_uint4(v[0] | (v[1] << 16), v[2] | (v[3] << 16), v[4] | (v[5] << 16), v[6] | (v[7] << 16));
    }
    __syncwarp();
}
__device__ __forceinline__ void conv_kgen_shift(uint8_t* wsp, int lane) {
#pragma unroll 1
    for (int G = lane; G < 258; G += 32) {
        const uint4 a = *(const uint4*)(wsp + CV_KE + 16 * G);
        const uint32_t nx = G < 257 ? *(const uint32_t*)(wsp + CV_KE + 16 * G + 16) : 0u;
        *(uint4*)(wsp + CV_KO + 16 * G) = make_uint4(__byte_perm(a.x, a.y, 0x5432), __byte_perm(a.y, a.z, 0x5432), __byte_perm(a.z, a.w, 0x5432), __byte_perm(a.w, nx, 0x5432));
    }
    __syncwarp();
}

__device__ __forceinline__ void conv_run(uint32_t ws, uint8_t* wsp, int lane) {
    const int g = lane >> 2, c = lane & 3;
    float acc[16][4];
#pragma unroll
    for (int j = 0; j < 16; j++) acc[j][0] = acc[j][1] = acc[j][2] = acc[j][3] = 0.f;
    const uint32_t kb = ws + ((g & 1) ? CV_KO : CV_KE) + ((g >> 1) + c) * 4;
#pragma unroll 1
    for (int r = 0; r < 8; r++) {
        uint32_t H[16][2];
        {
            const int m = lane >> 3, n = lane & 7;
            const int pc0 = 8 * (m >> 1) + n - r + 8;
            const uint32_t ua = ws + CV_U + 32 * pc0 + 16 * ((m & 1) ^ ((pc0 >> 2) & 1));
#pragma unroll
            for (int i = 0; i < 8; i++) ldsm_x4(H[2 * i][0], H[2 * i][1], H[2 * i + 1][0], H[2 * i + 1][1], ua + i * 512);
        }
        const uint32_t ka = kb + r * 32;
        uint32_t a[2][4];
        a[0][0] = lds32v(ka); a[0][1] = lds32v(ka + 16); a[0][2] = lds32v(ka + 16); a[0][3] = lds32v(ka + 32);
#pragma unroll
        for (int q = 0; q < 16; q++) {
            if (q < 15) {
                const uint32_t kn = ka + 256 * (q + 1);
                a[(q + 1) & 1][0] = lds32v(kn); a[(q + 1) & 1][1] = lds32v(kn + 16); a[(q + 1) & 1][2] = lds32v(kn + 16); a[(q + 1) & 1][3] = lds32v(kn + 32);
            }
#pragma unroll
            for (int j = q; j < 16; j++) mma_bf16(acc[j], a[q & 1][0], a[q & 1][1], a[q & 1][2], a[q & 1][3], H[j - q][0], H[j - q][1]);
        }
    }
    __syncwarp();
    uint16_t* ys = (uint16_t*)(wsp + CV_KE);
#pragma unroll
    for (int j = 0; j < 16; j++)
#pragma unroll
        for (int e = 0; e < 4; e++)
            ys[16 * (8 * j + 2 * c + (e & 1)) + g + 8 * (e >> 1)] = __bfloat16_as_ushort(__float2bfloat16(acc[j][e]));
}

constexpr int CV_RAW = 4 * CV_WARP_B;
constexpr int CV_BAR = CV_RAW + 16384;
constexpr int CV_GROUP_B = CV_BAR + 128;

__device__ __forceinline__ void conv_transpose(uint32_t sb, int half, int sub, int t128) {
#pragma unroll 2
    for (int it = 0; it < 4; it++) {
        const int tl = 2 * (t128 + 128 * it), t = tl + 1024 * half;
        uint32_t x0, y0, x1, y1;
        asm volatile("ld.shared.v2.b32 {%0, %1}, [%2];" : "=r"(x0), "=r"(y0) : "r"(sb + CV_RAW + tl * 16 + sub));
        asm volatile("ld.shared.v2.b32 {%0, %1}, [%2];" : "=r"(x1), "=r"(y1) : "r"(sb + CV_RAW + tl * 16 + 16 + sub));
        const int pc = (t >> 4) + 8, kap = 14 - (t & 15);
        const uint32_t a = sb + CV_U + 32 * pc + 16 * ((kap >> 3) ^ ((pc >> 2) & 1)) + 2 * (kap & 7);
        sts32(a, __byte_perm(x1, x0, 0x5410));
        sts32(a + CV_WARP_B, __byte_perm(x1, x0, 0x7632));
        sts32(a + 2 * CV_WARP_B, __byte_perm(y1, y0, 0x5410));
        sts32(a + 3 * CV_WARP_B, __byte_perm(y1, y0, 0x7632));
    }
}

__device__ __forceinline__ void load_state_params(const ConvParams& P, int i, uint32_t& pa, uint32_t& pb, uint32_t& pc) {
    pa = (uint32_t)__ldg((const uint16_t*)P.Are + i) | ((uint32_t)__ldg((const uint16_t*)P.Aim + i) << 16);
    pb = (uint32_t)__ldg((const uint16_t*)P.Bre + i) | ((uint32_t)__ldg((const uint16_t*)P.Bim + i) << 16);
    pc = (uint32_t)__ldg((const uint16_t*)P.Cre + i) | ((uint32_t)__ldg((const uint16_t*)P.Cim + i) << 16);
}
constexpr int CV_PART = CV_U + 256;
constexpr int BARID_H = 7;

__device__ __forceinline__ void conv_helper(const ConvParams& P, int d, int ch, uint32_t stage, float* part, int lane, int pair_bar) {
    uint32_t pa, pb, pc;
    load_state_params(P, d * NST + ch * 32 + lane, pa, pb, pc);
    const float dt = __bfloat162float(__float2bfloat16(expf(__bfloat162float(P.logdt[d]))));
    float acc[2][3][4];
#pragma unroll
    for (int i = 0; i < 24; i++) (&acc[0][0][0])[i] = 0.f;
    conv_kgen_chunk(acc, dt, pa, pb, pc, stage, lane);
    if (ch == 2) {
#pragma unroll
        for (int i = 0; i < 24; i++) part[i * 32 + lane] = (&acc[0][0][0])[i];
        named_arrive(pair_bar, 64);
    } else {
        named_sync(pair_bar, 64);
#pragma unroll
        for (int i = 0; i < 24; i++) part[i * 32 + lane] += (&acc[0][0][0])[i];
    }
    fence_async_smem();
    named_arrive(BARID_H, 384);
}

__device__ __forceinline__ void conv_group(const ConvParams& P, const CUtensorMap* tmU, int d0, uint32_t sb, uint8_t* smem, int t128, int bar,
                                           bool helpers, bool wait_store) {
    const int lane = t128 & 31, warp = t128 >> 5, d = d0 + warp;
    const uint32_t ws = sb + warp * CV_WARP_B, mb = sb + CV_BAR;
    uint8_t* wsp = smem + warp * CV_WARP_B;
    if (t128 == 0) {
        mbar_init(mb, 1);
        asm volatile("fence.mbarrier_init.release.cluster;" ::: "memory");
        fence_async_smem();
    }
    uint32_t pa[4], pb[4], pc[4];
#pragma unroll
    for (int ch = 0; ch < 4; ch++) {
        pa[ch] = pb[ch] = pc[ch] = 0u;
        if (ch < 2 || !helpers) load_state_params(P, d * NST + ch * 32 + lane, pa[ch], pb[ch], pc[ch]);
    }
    const float ldt = __bfloat162float(P.logdt[d]), dsk = __bfloat162float(P.Dskip[d]);
    sts32(ws + CV_U + lane * 4, 0u); sts32(ws + CV_U + 128 + lane * 4, 0u);
    const float dt = __bfloat162float(__float2bfloat16(expf(ldt)));
    float acc[2][3][4];
#pragma unroll
    for (int i = 0; i < 24; i++) (&acc[0][0][0])[i] = 0.f;
    named_sync(bar, 128);
    auto load_u = [&](int half) {
        if (t128 == 0) {
            mbar_expect_tx(mb, 16384);
#pragma unroll 1
            for (int j = 0; j < 4; j++) tma_2d(sb + CV_RAW + j * 4096, tmU, d0 & ~7, 1024 * half + j * 256, mb);
        }
    };
    load_u(0);
    const int nch = helpers ? 2 : 4;
#pragma unroll 1
    for (int ch = 0; ch < nch; ch++) {
        conv_kgen_chunk(acc, dt, pa[0], pb[0], pc[0], ws, lane);
        pa[0] = pa[1]; pa[1] = pa[2]; pa[2] = pa[3];
        pb[0] = pb[1]; pb[1] = pb[2]; pb[2] = pb[3];
        pc[0] = pc[1]; pc[1] = pc[2]; pc[2] = pc[3];
    }
    if (helpers) {
        named_sync(BARID_H, 384);
#pragma unroll
        for (int i = 0; i < 24; i++) (&acc[0][0][0])[i] += *(const float*)(wsp + CV_PART + (i * 32 + lane) * 4);
        named_sync(bar, 128);
    }
    mbar_wait(mb, 0);
    conv_transpose(sb, 0, (d0 & 4) * 2, t128);
    fence_async_smem();
    named_sync(bar, 128);
    load_u(1);
    conv_kgen_finish(acc, dsk, ws, wsp, lane);
    conv_kgen_shift(wsp, lane);
    mbar_wait(mb, 1);
    conv_transpose(sb, 1, (d0 & 4) * 2, t128);
    named_sync(bar, 128);
    conv_run(ws, wsp, lane);
    fence_async_smem();
    __syncwarp();
    if (lane == 0) {
        bulk_s2g(g_bT + (size_t)d * S_, ws + CV_KE, S_ * 2);
        bulk_commit();
        if (wait_store) bulk_wait0(); else asm volatile("cp.async.bulk.wait_group.read 0;" ::: "memory");
    }
    named_sync(bar, 128);
    if (t128 == 0) asm volatile("mbarrier.inval.shared::cta.b64 [%0];" ::"r"(mb) : "memory");
}

constexpr int KVT_B = 2 * KT_B;
constexpr int ATT_WO_B = 72 * 18 * 128;
constexpr int ATT_ORING = ATT_WO_B, ATT_BT = ATT_ORING + 3 * 8192, ATT_BAR = ATT_ORING + 6 * 8192;
constexpr int BAR_KV = 0, BAR_WO = 128, BAR_OF = 160, BAR_OE = 208, BAR_BT = 256, CNT_REL = 264;
constexpr int ATT_SMEM = (3 * CV_GROUP_B > ATT_BAR + 512 ? 3 * CV_GROUP_B : ATT_BAR + 512) + 1024;
static_assert(ATT_SMEM <= 232448 && ATT_BT % 1024 == 0 && ATT_ORING % 1024 == 0, "k2 smem");

__device__ __forceinline__ void load_q_raw(uint32_t (&q)[6], int h, int row0, int lane) {
    const uint32_t* qp = (const uint32_t*)g_Qp + ((size_t)h * 256 + (row0 >> 3)) * 96 + lane;
    q[0] = qp[0]; q[1] = qp[96]; q[2] = qp[32]; q[3] = qp[96 + 32]; q[4] = qp[64]; q[5] = qp[96 + 64];
}
__device__ __forceinline__ int prep_q(uint32_t (&q)[6], int lane, float kmax2) {
    const int c = lane & 3;
    float n0 = bf_lo(q[0]) * bf_lo(q[0]) + bf_hi(q[0]) * bf_hi(q[0]) + bf_lo(q[2]) * bf_lo(q[2]) + bf_hi(q[2]) * bf_hi(q[2]);
    float n1 = bf_lo(q[1]) * bf_lo(q[1]) + bf_hi(q[1]) * bf_hi(q[1]) + bf_lo(q[3]) * bf_lo(q[3]) + bf_hi(q[3]) * bf_hi(q[3]);
    if (c == 0) {
        n0 += bf_lo(q[4]) * bf_lo(q[4]) + bf_hi(q[4]) * bf_hi(q[4]);
        n1 += bf_lo(q[5]) * bf_lo(q[5]) + bf_hi(q[5]) * bf_hi(q[5]);
    }
    n0 += __shfl_xor_sync(~0u, n0, 1); n0 += __shfl_xor_sync(~0u, n0, 2);
    n1 += __shfl_xor_sync(~0u, n1, 1); n1 += __shfl_xor_sync(~0u, n1, 2);
    float b0, b1;
    asm("sqrt.approx.f32 %0, %1;" : "=f"(b0) : "f"(n0 * kmax2));
    asm("sqrt.approx.f32 %0, %1;" : "=f"(b1) : "f"(n1 * kmax2));
    b0 = b0 * 1.0005f + 0.002f; b1 = b1 * 1.0005f + 0.002f;
    const float m0 = ceilf((b0 - 15.9f) * 8.f) * 0.125f, m1 = ceilf((b1 - 15.9f) * 8.f) * 0.125f;
    q[4] = c == 0 ? q[4] : (c == 1 ? pack_bf16(-m0, 1.f) : (c == 2 ? 0x00003F80u : 0u));
    q[5] = c == 0 ? q[5] : (c == 1 ? pack_bf16(-m1, 1.f) : (c == 2 ? 0x00003F80u : 0u));
    const bool over = !(b0 <= 31.f && b1 <= 31.f), wide = b0 > 15.35f || b1 > 15.35f;
    return __any_sync(~0u, over) ? 2 : (__any_sync(~0u, wide) ? 1 : 0);
}

__device__ __forceinline__ bool wg_any(bool v, int bar) {
    uint32_t r;
    asm volatile("{\n.reg .pred p, q;\nsetp.ne.u32 q, %1, 0;\nbar.red.or.pred p, %2, 128, q;\nselp.u32 %0, 1, 0, p;\n}" : "=r"(r) : "r"((uint32_t)v), "r"(bar) : "memory");
    return r != 0;
}
__device__ __forceinline__ uint32_t sub_bf16(uint32_t a, uint32_t b) { uint32_t r; asm("sub.rn.bf16x2 %0, %1, %2;" : "=r"(r) : "r"(a), "r"(b)); return r; }
__device__ __forceinline__ uint32_t mix_bf16(uint32_t g, uint32_t h, uint32_t a, uint32_t b) {
    uint32_t t, u, r;
    asm("mul.rn.bf16x2 %0, %1, %2;" : "=r"(t) : "r"(g), "r"(a));
    asm("mul.rn.bf16x2 %0, %1, %2;" : "=r"(u) : "r"(h), "r"(b));
    asm("add.rn.bf16x2 %0, %1, %2;" : "=r"(r) : "r"(t), "r"(u));
    return r;
}
__device__ __forceinline__ float bf16r(float v) { return __bfloat162float(__float2bfloat16(v)); }

__device__ __noinline__ void attn_exact(const __nv_bfloat16* x, const __nv_bfloat16* wqkv, int h, int qb, uint8_t* smem) {
    const int tid = threadIdx.x;
    uint32_t* kv = (uint32_t*)smem;
    uint32_t* sw = kv + S_ * 18;
    for (int i = tid; i < D_ * 27; i += 512) {
        const int k = i / 27, j = i % 27;
        sw[i] = *(const uint32_t*)(wqkv + (size_t)k * 1728 + (j / 9) * 576 + h * DH + 2 * (j % 9));
    }
    __syncthreads();
    for (int r = 0; r < 4; r++) {
        const int j = tid + 512 * r;
        float acc[36];
#pragma unroll
        for (int i = 0; i < 36; i++) acc[i] = 0.f;
        for (int k = 0; k < D_; k++) {
            const float xv = __bfloat162float(x[(size_t)j * D_ + k]);
#pragma unroll
            for (int w = 0; w < 18; w++) { const uint32_t u = sw[k * 27 + 9 + w]; acc[2 * w] = fmaf(xv, bf_lo(u), acc[2 * w]); acc[2 * w + 1] = fmaf(xv, bf_hi(u), acc[2 * w + 1]); }
        }
#pragma unroll
        for (int w = 0; w < 18; w++) kv[j * 18 + w] = pack_bf16(acc[2 * w], acc[2 * w + 1]);
    }
    const int row = qb * 512 + tid;
    float q[18], o[18];
#pragma unroll
    for (int i = 0; i < 18; i++) q[i] = o[i] = 0.f;
    for (int k = 0; k < D_; k++) {
        const float xv = __bfloat162float(x[(size_t)row * D_ + k]);
#pragma unroll
        for (int w = 0; w < 9; w++) { const uint32_t u = sw[k * 27 + w]; q[2 * w] = fmaf(xv, bf_lo(u), q[2 * w]); q[2 * w + 1] = fmaf(xv, bf_hi(u), q[2 * w + 1]); }
    }
#pragma unroll
    for (int i = 0; i < 18; i++) q[i] = bf16r(q[i]);
    __syncthreads();
    auto score = [&](int j) {
        float s = 0.f;
#pragma unroll
        for (int w = 0; w < 9; w++) { const uint32_t u = kv[j * 18 + w]; s = fmaf(q[2 * w], bf_lo(u), s); s = fmaf(q[2 * w + 1], bf_hi(u), s); }
        return bf16r(bf16r(s) * 0.23570226039551584f);
    };
    float m = -INFINITY, l = 0.f;
    for (int j = 0; j < S_; j++) m = fmaxf(m, score(j));
    for (int j = 0; j < S_; j++) l += expf(score(j) - m);
    for (int j = 0; j < S_; j++) {
        const float p = bf16r(expf(score(j) - m) / l);
#pragma unroll
        for (int w = 0; w < 9; w++) { const uint32_t u = kv[j * 18 + 9 + w]; o[2 * w] = fmaf(p, bf_lo(u), o[2 * w]); o[2 * w + 1] = fmaf(p, bf_hi(u), o[2 * w + 1]); }
    }
#pragma unroll
    for (int w = 0; w < 9; w++) *(uint32_t*)(g_O + (size_t)row * D_ + h * DH + 2 * w) = pack_bf16(o[2 * w], o[2 * w + 1]);
    __syncthreads();
}

struct TrueT { static constexpr bool value = true; };
struct FalseT { static constexpr bool value = false; };
__device__ __forceinline__ void spin_until(const uint32_t* p, uint32_t target) {
    for (int it = 0;; it++) {
        uint32_t v;
        asm volatile("ld.relaxed.gpu.global.u32 %0, [%1];" : "=r"(v) : "l"(p) : "memory");
        if (v >= target) break;
        if (it > (1 << 24)) __trap();
        __nanosleep(20);
    }
    asm volatile("fence.acq_rel.gpu;" ::: "memory");
}
__device__ __forceinline__ void load_wo_group(int i, int cb, uint32_t sb) {
    const uint32_t bar = sb + ATT_BAR + BAR_WO + 8 * i;
    const uint32_t n = i < 3 ? 4 * KVT_B : ATT_WO_B - 12 * KVT_B;
    mbar_expect_tx(bar, n);
    bulk_g2s(sb + 4 * KVT_B * i, (const uint8_t*)g_WoT + (size_t)cb * ATT_WO_B + 4 * KVT_B * i, n, bar);
}

__global__ void __launch_bounds__(512, 1) attn_kernel(const __grid_constant__ CUtensorMap tmU, const __grid_constant__ CUtensorMap tmO,
                                                       const __grid_constant__ CUtensorMap tmBT, const __grid_constant__ CUtensorMap tmOut,
                                                       const __grid_constant__ ConvParams P, const __nv_bfloat16* __restrict__ wqkv) {
    extern __shared__ uint8_t smem_raw[];
    const uint32_t sb = (smem_u32(smem_raw) + 1023) & ~1023u;
    uint8_t* smem = smem_raw + (sb - smem_u32(smem_raw));
    if (blockIdx.x < 4) {
        const int w = threadIdx.x >> 7;
        if (w < 3) {
            conv_group(P, &tmU, (132 + blockIdx.x * 3 + w) * 4, sb + w * CV_GROUP_B, smem + w * CV_GROUP_B, threadIdx.x & 127, 1 + w, false, true);
            if ((threadIdx.x & 127) == 0) {
                pdl_wait();
                asm volatile("fence.proxy.async.global;" ::: "memory");
                __threadfence();
                atomicAdd(&g_cnt[32], 1u);
            }
        }
        return;
    }
    const int bid = blockIdx.x - 4, h = bid >> 2, qb = bid & 3;
    const int tid = threadIdx.x, lane = tid & 31, c = lane & 3;
    const int wg = __shfl_sync(~0u, tid >> 7, 0), warp = __shfl_sync(~0u, (tid >> 5) & 3, 0);
    const uint32_t barb = sb + ATT_BAR;
    if (tid < 16) mbar_init(barb + BAR_KV + 8 * tid, 1);
    else if (tid < 26) mbar_init(barb + BAR_WO + 8 * (tid - 16), 1);
    else if (tid < 32) mbar_init(barb + BAR_OE + 8 * (tid - 26), 2);
    else if (tid == 32) mbar_init(barb + BAR_BT, 1);
    else if (tid < 37) ((uint32_t*)(smem + ATT_BAR + CNT_REL))[tid - 33] = 0u;
    asm volatile("fence.mbarrier_init.release.cluster;" ::: "memory");
    __syncthreads();
    pdl_wait();
    auto load_kv = [&](int kt) {
        mbar_expect_tx(barb + BAR_KV + 8 * kt, KVT_B);
        bulk_g2s(sb + kt * KVT_B, (const uint8_t*)g_KV + ((size_t)h * 16 + kt) * KVT_B, KVT_B, barb + BAR_KV + 8 * kt);
    };
    if (tid < KV_FIRST) load_kv(tid);
    const int rowbase = qb * 512 + warp * 16 + wg * 128;
    uint32_t q1[4], q2[4], qn[6];
    int cls, clsn;
    uint32_t vmax;
    {
        uint32_t q[6];
        const float kv = lane < 16 ? g_kmax2[lane * H_ + h] : 0.f;
        const uint32_t vv = lane < 16 ? g_vmax[lane * H_ + h] : 0u;
        load_q_raw(q, h, rowbase, lane);
        load_q_raw(qn, h, rowbase + 64, lane);
        vmax = __reduce_max_sync(~0u, vv);
        const float kmax2 = __uint_as_float(__reduce_max_sync(~0u, __float_as_uint(kv)));
        cls = prep_q(q, lane, kmax2);
        clsn = prep_q(qn, lane, kmax2);
#pragma unroll
        for (int i = 0; i < 4; i++) q1[i] = q[i];
        q2[0] = q[4]; q2[1] = q[5]; q2[2] = q2[3] = 0u;
        asm volatile("" : "+r"(q2[2]), "+r"(q2[3]));
    }
    const bool bad = __syncthreads_or(cls == 2 || clsn == 2 || vmax >= 0x7C00u || vmax < 0x0C00u);
    bool lbad = false;
    const int rt = qb * 8 + (h >> 2), cb = h & 3;
    if (!bad) {
        uint32_t kOne = 0x3C003C00u, kTop = 0x38a438a4u;
        float s[32], o[12];
        uint32_t p[16], pb[16];
#pragma unroll
        for (int i = 0; i < 12; i++) o[i] = 0.f;
#pragma unroll
        for (int i = 0; i < 32; i++) s[i] = 0.f;
        uint64_t dk[4], dv[8];
        dk[0] = mkdesc(sb + 8 * GROUP_B, 128, GROUP_B); dk[1] = mkdesc(sb + 8 * GROUP_B + 256, 0, GROUP_B);
        dk[2] = mkdesc(sb, 128, GROUP_B); dk[3] = mkdesc(sb + 256, 0, GROUP_B);
#pragma unroll
        for (int i = 0; i < 8; i++) dv[i] = mkdesc(sb + KT_B + 2 * i * GROUP_B, GROUP_B, 128);
        mbar_wait(barb + BAR_KV, 0);
        reg_fence(s); reg_fence(o); reg_fence_u(q1); reg_fence_u(q2);
        wg_fence();
        wgmma_qk_n64(s, q1[0], q1[1], q1[2], q1[3], dk[2], 0);
        wgmma_qk_n64(s, q2[0], q2[1], q2[2], q2[3], dk[3], 1);
        wg_commit();
        desc_bump(dk[2], 768); desc_bump(dk[3], 768);
        wg_wait<0>();
        reg_fence(s); reg_fence(o);
        auto exp_step = [&](uint32_t (&pp)[16], auto clamp) {
#pragma unroll
            for (int j = 0; j < 8; j++) {
                if (is_mufu(j)) {
                    pp[2 * j] = pack_f16(ex2f(s[4 * j]), ex2f(s[4 * j + 1]));
                    pp[2 * j + 1] = pack_f16(ex2f(s[4 * j + 2]), ex2f(s[4 * j + 3]));
                } else {
                    pp[2 * j] = exp2_pair_poly<decltype(clamp)::value>(s[4 * j], s[4 * j + 1], kOne, kTop);
                    pp[2 * j + 1] = exp2_pair_poly<decltype(clamp)::value>(s[4 * j + 2], s[4 * j + 3], kOne, kTop);
                }
            }
        };
        auto mma_step = [&](uint32_t (&pp)[16], int first, uint64_t& k1, uint64_t& k2, uint64_t& v0, uint64_t& v1, uint64_t& v2, uint64_t& v3) {
            reg_fence(s); reg_fence_u(pp); reg_fence_u(q1); reg_fence_u(q2);
            wg_fence();
            wgmma_qk_n64(s, q1[0], q1[1], q1[2], q1[3], k1, 0);
            wgmma_qk_n64(s, q2[0], q2[1], q2[2], q2[3], k2, 1);
            wg_commit();
            wgmma_pv_n24(o, pp[0], pp[1], pp[2], pp[3], v0, first);
            wgmma_pv_n24(o, pp[4], pp[5], pp[6], pp[7], v1, 1);
            wgmma_pv_n24(o, pp[8], pp[9], pp[10], pp[11], v2, 1);
            wgmma_pv_n24(o, pp[12], pp[13], pp[14], pp[15], v3, 1);
            wg_commit();
            desc_bump(k1, 768); desc_bump(k2, 768);
            desc_bump(v0, 768); desc_bump(v1, 768); desc_bump(v2, 768); desc_bump(v3, 768);
            wg_wait<1>();
            reg_fence(s);
        };
        auto release = [&](int i) {
            if ((tid & 127) == 0 && atomicAdd((uint32_t*)(smem + ATT_BAR + CNT_REL) + i, 1u) == 3u) load_wo_group(i, cb, sb);
        };
        auto pass = [&](int si, auto clamp) {
            int first = 0;
#pragma unroll 1
            for (int kt = 0; kt < 16; kt++) {
                exp_step(p, clamp);
                mma_step(p, first, dk[0], dk[1], dv[0], dv[1], dv[2], dv[3]);
                first = 1;
                exp_step(pb, clamp);
                if (kt == 15) {
                    desc_bump(dk[2], (uint32_t)(-16 * 768)); desc_bump(dk[3], (uint32_t)(-16 * 768));
                    if (si == 0) {
#pragma unroll
                        for (int i = 0; i < 4; i++) q1[i] = qn[i];
                        q2[0] = qn[4]; q2[1] = qn[5];
                    }
                } else if (si == 0) {
                    if ((tid & 127) == 0 && (kt & 3) == wg && kt + KV_FIRST < 16) load_kv(kt + KV_FIRST);
                    mbar_wait(barb + BAR_KV + 8 * (kt + 1), 0);
                } else if ((kt & 3) == 0 && kt) {
                    release((kt >> 2) - 1);
                }
                mma_step(pb, 1, dk[2], dk[3], dv[4], dv[5], dv[6], dv[7]);
            }
        };
        const int clamp_mask = (wg_any(cls != 0, 1 + wg) ? 1 : 0) | (wg_any(clsn != 0, 1 + wg) ? 2 : 0);
#pragma unroll 1
        for (int si = 0; si < 2; si++) {
            if (clamp_mask >> si & 1) pass(si, TrueT{}); else pass(si, FalseT{});
            wg_wait<0>();
            reg_fence(o); reg_fence(s); reg_fence_u(p); reg_fence_u(pb);
            if (si == 1) release(3);
            desc_bump(dk[0], (uint32_t)(-16 * 768)); desc_bump(dk[1], (uint32_t)(-16 * 768));
#pragma unroll
            for (int i = 0; i < 8; i++) desc_bump(dv[i], (uint32_t)(-16 * 768));
            const float l0 = shfl_idx_f(o[8], (lane & ~3) | 1), l1 = shfl_idx_f(o[10], (lane & ~3) | 1);
            lbad |= !(l0 >= 64.f && l0 < INFINITY && l1 >= 64.f && l1 < INFINITY);
            const float r0 = __fdividef(1.f, l0), r1 = __fdividef(1.f, l1);
            const int row = rowbase + si * 64 + (lane >> 2);
            uint32_t* o0 = (uint32_t*)(g_O + (size_t)row * D_ + h * DH) + c;
            uint32_t* o1 = o0 + 8 * D_ / 2;
            o0[0] = pack_bf16(o[0] * r0, o[1] * r0); o1[0] = pack_bf16(o[2] * r1, o[3] * r1);
            o0[4] = pack_bf16(o[4] * r0, o[5] * r0); o1[4] = pack_bf16(o[6] * r1, o[7] * r1);
            if (c == 0) { o0[8] = pack_bf16(o[8] * r0, o[9] * r0); o1[8] = pack_bf16(o[10] * r1, o[11] * r1); }
        }
    }
    uint32_t wo_par = 0;
    if (__syncthreads_or(bad || lbad)) {
        if (bad) { for (int i = 0; i < KV_FIRST; i++) mbar_wait(barb + BAR_KV + 8 * i, 0); }
        else { for (int i = 0; i < 4; i++) mbar_wait(barb + BAR_WO + 8 * i, 0); wo_par = 1; }
        __syncthreads();
        attn_exact(P.x, wqkv, h, qb, smem);
        fence_async_smem();
        __syncthreads();
        if (tid < 4) load_wo_group(tid, cb, sb);
    }
    __syncthreads();
    if (tid < 8) {
        asm volatile("fence.proxy.async.global;" ::: "memory");
        asm volatile("fence.acq_rel.gpu;" ::: "memory");
        asm volatile("red.relaxed.gpu.global.add.u32 [%0], 1;" ::"l"(&g_cnt[qb * 8 + tid]) : "memory");
    }
    if (wg == 2) {
        if (tid == 256) {
            spin_until(&g_cnt[rt], 32);
            asm volatile("fence.proxy.async.global;" ::: "memory");
#pragma unroll 1
            for (int kb = 0; kb < 9; kb++) {
                const int st = kb < 6 ? kb : kb - 6;
                if (kb >= 6) mbar_wait(barb + BAR_OE + 8 * st, 0);
                mbar_expect_tx(barb + BAR_OF + 8 * st, 8192);
                tma_2d(sb + ATT_ORING + st * 8192, &tmO, kb * 64, rt * 64, barb + BAR_OF + 8 * st);
            }
            spin_until(&g_cnt[32], 12);
            asm volatile("fence.proxy.async.global;" ::: "memory");
            for (int st = 3; st < 6; st++) mbar_wait(barb + BAR_OE + 8 * st, 0);
            mbar_expect_tx(barb + BAR_BT, 144 * 128);
            tma_2d(sb + ATT_BT, &tmBT, rt * 64, cb * 144, barb + BAR_BT);
        }
    } else if (wg < 2) {
        const int g = lane >> 2;
        const int row = rt * 64 + warp * 16 + g;
        const uint32_t g0 = g_gate[row], g1 = g_gate[row + 8];
        const uint32_t h0 = sub_bf16(0x3F803F80u, g0), h1 = sub_bf16(0x3F803F80u, g1);
        float acc[36];
#pragma unroll
        for (int i = 0; i < 36; i++) acc[i] = 0.f;
#pragma unroll 1
        for (int i = 0; i < 4; i++) mbar_wait(barb + BAR_WO + 8 * i, wo_par);
#pragma unroll 1
        for (int kb = 0; kb < 9; kb++) {
            const int st = kb < 6 ? kb : kb - 6;
            mbar_wait(barb + BAR_OF + 8 * st, kb >= 6);
            reg_fence(acc);
            wg_fence();
#pragma unroll
            for (int ks = 0; ks < 4; ks++)
                wgmma_ss_n72_tb(acc, mkdesc_sw128(sb + ATT_ORING + st * 8192 + ks * 32, 16, 1024),
                                mkdesc(sb + (8 * kb + 2 * ks) * 2304 + wg * 9 * 128, 2304, 128), 1);
            wg_commit();
            if (kb > 0) {
                wg_wait<1>();
                if ((tid & 127) == 0 && kb <= 6) mbar_arrive(barb + BAR_OE + 8 * (kb - 1));
            }
        }
        wg_wait<0>();
        reg_fence(acc);
        mbar_wait(barb + BAR_BT, 0);
        const uint32_t bt = sb + ATT_BT + (wg * 72 + (lane & 7)) * 128;
        const uint32_t ch0 = (uint32_t)(((2 * warp + ((lane >> 3) & 1)) ^ (lane & 7)) << 4);
        const uint32_t st0 = sb + ATT_ORING + (warp * 16 + g) * 288 + (wg * 72 + 2 * c) * 2;
        named_sync(5, 256);
#pragma unroll
        for (int jp = 0; jp < 5; jp++) {
            uint32_t b[4];
            const int jj = 2 * jp + (jp < 4 ? (lane >> 4) : 0);
            asm volatile("ldmatrix.sync.aligned.m8n8.x4.trans.shared.b16 {%0, %1, %2, %3}, [%4];"
                         : "=r"(b[0]), "=r"(b[1]), "=r"(b[2]), "=r"(b[3]) : "r"(bt + jj * 1024 + ch0) : "memory");
#pragma unroll
            for (int u = 0; u < 2; u++) {
                const int j2 = 2 * jp + u;
                if (j2 < 9) {
                    sts32(st0 + 16 * j2, mix_bf16(g0, h0, pack_bf16(acc[4 * j2], acc[4 * j2 + 1]), b[2 * u]));
                    sts32(st0 + 8 * 288 + 16 * j2, mix_bf16(g1, h1, pack_bf16(acc[4 * j2 + 2], acc[4 * j2 + 3]), b[2 * u + 1]));
                }
            }
        }
        fence_async_smem();
        named_sync(5, 256);
        if (tid == 0) {
            asm volatile("cp.async.bulk.tensor.2d.global.shared::cta.bulk_group [%0, {%2, %3}], [%1];"
                         ::"l"(&tmOut), "r"(sb + ATT_ORING), "r"(cb * 144), "r"(rt * 64) : "memory");
            bulk_commit();
            asm volatile("cp.async.bulk.wait_group.read 0;" ::: "memory");
        }
    }
}

constexpr int G1_STAGES = 3, G1_STAGE_B = 16384 + 32768;
constexpr int G1_SMEM_CONV = G1_STAGES * G1_STAGE_B;
constexpr int G1_SMEM_BAR = G1_SMEM_CONV + CV_GROUP_B, G1_SMEM_RED = G1_SMEM_BAR + 128, G1_SMEM = G1_SMEM_RED + 64 + 1024;
static_assert(G1_SMEM <= 232448, "k1 smem");

__host__ __device__ constexpr int col_delta(int jj, int c) {
    const int col = 8 * jj + 2 * c, lh = col / 18, dd = col % 18;
    return lh * 6144 + (dd >> 3) * 128 + (dd & 7) * 2 - 4 * c;
}
template <int JJ> __device__ __forceinline__ uint32_t col_addr(uint32_t base_c, int c) {
    constexpr int d0 = col_delta(JJ, 0), d1 = col_delta(JJ, 1), d2 = col_delta(JJ, 2), d3 = col_delta(JJ, 3);
    uint32_t a = base_c + d0;
    if (d1 != d0) a += c >= 1 ? d1 - d0 : 0;
    if (d2 != d1) a += c >= 2 ? d2 - d1 : 0;
    if (d3 != d2) a += c >= 3 ? d3 - d2 : 0;
    return a;
}
template <int JJ> __device__ __forceinline__ void stage_cols(const float (&acc)[108], uint32_t base_c, int c, const float (&sc)[3], const bool (&f16)[3]) {
    if constexpr (JJ < 27) {
        constexpr int z = JJ / 9;
        const uint32_t a = col_addr<JJ>(base_c, c);
        const float v0 = acc[4 * JJ] * sc[z], v1 = acc[4 * JJ + 1] * sc[z], v2 = acc[4 * JJ + 2] * sc[z], v3 = acc[4 * JJ + 3] * sc[z];
        uint32_t r0, r1;
        if (f16[z]) { r0 = pack_f16(v0, v1); r1 = pack_f16(v2, v3); } else { r0 = pack_bf16(v0, v1); r1 = pack_bf16(v2, v3); }
        sts32(a, r0);
        sts32(a + GROUP_B, r1);
        stage_cols<JJ + 1>(acc, base_c, c, sc, f16);
    }
}

__global__ void __launch_bounds__(384, 1) qkv_kernel(const __grid_constant__ CUtensorMap tmX, const __grid_constant__ CUtensorMap tmW,
                                                      const __grid_constant__ CUtensorMap tmU, const __grid_constant__ ConvParams P,
                                                      const __nv_bfloat16* __restrict__ gate_w, const __nv_bfloat16* __restrict__ wo) {
    extern __shared__ uint8_t smem_raw[];
    const uint32_t sb = (smem_u32(smem_raw) + 1023) & ~1023u;
    uint8_t* smem = smem_raw + (sb - smem_u32(smem_raw));
    const int tid = threadIdx.x, lane = tid & 31;
    const int wg = __shfl_sync(~0u, tid >> 7, 0), warp = __shfl_sync(~0u, (tid >> 5) & 3, 0);
    const int mt = blockIdx.x >> 3, nt = blockIdx.x & 7;
    const uint32_t full = sb + G1_SMEM_BAR, empty = full + 8 * G1_STAGES;

    if (wg == 2) {
        if (blockIdx.x < 128) {
        const int row = blockIdx.x * 16 + warp * 4;
        const uint32_t* xr = (const uint32_t*)(P.x + (size_t)row * D_);
        float a[4] = {0.f, 0.f, 0.f, 0.f};
#pragma unroll
        for (int i = 0; i < 9; i++) {
            const uint32_t gw = __ldg((const uint32_t*)gate_w + lane + 32 * i);
#pragma unroll
            for (int r = 0; r < 4; r++) {
                const uint32_t v = __ldg(xr + r * (D_ / 2) + lane + 32 * i);
                a[r] = fmaf(bf_lo(v), bf_lo(gw), a[r]); a[r] = fmaf(bf_hi(v), bf_hi(gw), a[r]);
            }
        }
#pragma unroll
        for (int o = 16; o; o >>= 1)
#pragma unroll
            for (int r = 0; r < 4; r++) a[r] += __shfl_xor_sync(~0u, a[r], o);
        if (lane < 4) {
            const float z = __bfloat162float(__float2bfloat16(lane == 0 ? a[0] : lane == 1 ? a[1] : lane == 2 ? a[2] : a[3]));
            const float gv = 1.f / (1.f + __expf(-z));
            g_gate[row + lane] = pack_bf16(gv, gv);
        }
        }
        conv_group(P, &tmU, blockIdx.x * 4, sb + G1_SMEM_CONV, smem + G1_SMEM_CONV, tid & 127, 2, true, false);
        return;
    }
    const bool spare = blockIdx.x >= 128;
    auto issue = [&](int kb) {
        const int s = kb % G1_STAGES;
        const uint32_t st = sb + s * G1_STAGE_B;
        mbar_expect_tx(full + 8 * s, G1_STAGE_B);
        tma_2d(st, &tmX, kb * 64, mt * 128, full + 8 * s);
#pragma unroll 1
        for (int j = 0; j < 4; j++) tma_2d(st + 16384 + j * 8192, &tmW, nt * 216 + j * 64, kb * 64, full + 8 * s);
    };
    if (tid == 128 && !spare) {
        for (int i = 0; i < G1_STAGES; i++) { mbar_init(full + 8 * i, 1); mbar_init(empty + 8 * i, 2); }
        asm volatile("fence.mbarrier_init.release.cluster;" ::: "memory");
        fence_async_smem();
        issue(0);
    }
    if (tid < 12) ((uint32_t*)(smem + G1_SMEM_RED))[tid] = 0u;
    uint4 wv[2];
    int wj[2];
#pragma unroll
    for (int r = 0; r < 2; r++) {
        const int jl = tid + 256 * r, j = blockIdx.x * 324 + jl, ng = j % 18, k = (j / 18) % 576, cb = j / (18 * 576);
        wj[r] = (jl < 324 && !spare) ? ((cb * 72 + (k >> 3)) * 18 + ng) * 8 + (k & 7) : -1;
        if (wj[r] >= 0) wv[r] = __ldg((const uint4*)wo + k * 72 + cb * 18 + ng);
    }
    {
        const int hw = tid >> 5;
        const uint32_t stage = sb + G1_STAGE_B + hw * 8064;
        conv_helper(P, blockIdx.x * 4 + (hw >> 1), 2 + (hw & 1), stage, (float*)(smem + G1_SMEM_CONV + (hw >> 1) * CV_WARP_B + CV_PART), lane, 8 + (hw >> 1));
    }
#pragma unroll
    for (int r = 0; r < 2; r++) if (wj[r] >= 0) g_WoT[wj[r]] = wv[r];
    if (spare) {
        if (blockIdx.x == 128 && tid < 33) g_cnt[tid] = 0u;
        return;
    }
    fence_async_smem();
    named_sync(1, 256);
    if (tid == 128) { issue(1); issue(2); }
    const int w = wg;
    float acc[108];
#pragma unroll
    for (int i = 0; i < 108; i++) acc[i] = 0.f;
#pragma unroll 1
    for (int kb = 0; kb < 9; kb++) {
        const int s = kb % G1_STAGES;
        mbar_wait(full + 8 * s, (kb / G1_STAGES) & 1);
        const uint32_t st = sb + s * G1_STAGE_B;
        reg_fence(acc);
        wg_fence();
#pragma unroll
        for (int ks = 0; ks < 4; ks++)
            wgmma_ss_n216_tb(acc, mkdesc_sw128(st + w * 8192 + ks * 32, 16, 1024), mkdesc_sw128(st + 16384 + ks * 2048, 8192, 1024), 1);
        wg_commit();
        if (kb > 0) {
            wg_wait<1>();
            const int pk = kb - 1, ps = pk % G1_STAGES;
            if ((tid & 127) == 0) {
                mbar_arrive(empty + 8 * ps);
                if (tid == 128 && pk + G1_STAGES < 9) {
                    mbar_wait(empty + 8 * ps, (pk / G1_STAGES) & 1);
                    issue(pk + G1_STAGES);
                }
            }
            __syncwarp();
        }
    }
    wg_wait<0>();
    reg_fence(acc);
    pdl_launch_dependents();
    named_sync(1, 256);
    const int g = lane >> 2, c = lane & 3;
    const uint32_t rowoff = sb + (w * 8 + warp * 2) * GROUP_B + g * 16;
    const int gh0 = 12 * nt;
    {
        float sc[3]; bool f16[3];
#pragma unroll
        for (int z = 0; z < 3; z++) { const int ty = (gh0 + 4 * z) >> 5; sc[z] = ty == 0 ? QSCALE : 1.f; f16[z] = ty == 2; }
        stage_cols<0>(acc, rowoff + 4 * c, c, sc, f16);
    }
#pragma unroll 1
    for (int i = 0; i < 6; i++) {
        const int lh = 2 * i + w, row = tid & 127;
        const int ty = (gh0 + lh) >> 5;
        const uint32_t a = sb + lh * 6144 + (row >> 3) * GROUP_B + 256 + (row & 7) * 16;
        const bool poly = !is_mufu((row >> 3) & 15);
        const uint32_t w1 = ty == 1 ? (0x3F80u | (poly ? 0x46400000u : 0u)) : (ty == 2 ? 0x3C00u : 0u);
        const uint32_t w2 = (ty == 1 && poly) ? 0x4170u : 0u;
        sts32(a + 4, w1); sts32(a + 8, w2); sts32(a + 12, 0u);
    }
    fence_async_smem();
    named_sync(1, 256);
    if (tid < 12) {
        const int gh = gh0 + tid, ty = gh >> 5, h = gh & 31;
        uint8_t* dst = ty == 0 ? (uint8_t*)g_Qp + (size_t)h * HEAD_B + mt * 6144 : (uint8_t*)g_KV + ((size_t)h * 16 + mt) * 12288 + (ty - 1) * 6144;
        bulk_s2g(dst, sb + tid * 6144, 6144);
        bulk_commit();
    }
    if (nt >= 2) {
#pragma unroll 1
        for (int i = 0; i < 6; i++) {
            const int lh = 2 * i + w, row = tid & 127;
            const int ty = (gh0 + lh) >> 5;
            if (ty == 0) continue;
            const uint8_t* a = smem + lh * 6144 + (row >> 3) * GROUP_B + (row & 7) * 16;
            const uint4 u0 = *(const uint4*)a, u1 = *(const uint4*)(a + 128);
            const uint32_t u2 = *(const uint32_t*)(a + 256);
            const uint32_t u[9] = {u0.x, u0.y, u0.z, u0.w, u1.x, u1.y, u1.z, u1.w, u2};
            float m = 0.f;
            if (ty == 1) {
#pragma unroll
                for (int j = 0; j < 9; j++) { m = fmaf(bf_lo(u[j]), bf_lo(u[j]), m); m = fmaf(bf_hi(u[j]), bf_hi(u[j]), m); }
            } else {
                uint32_t mx = 0;
#pragma unroll
                for (int j = 0; j < 9; j++) mx = max(mx, max(u[j] & 0x7FFFu, (u[j] >> 16) & 0x7FFFu));
                m = __uint_as_float(mx);
            }
            const uint32_t mm = __reduce_max_sync(~0u, __float_as_uint(m) & 0x7FFFFFFFu);
            if (lane == 0) atomicMax((uint32_t*)(smem + G1_SMEM_RED) + lh, mm);
        }
        named_sync(1, 256);
        if (tid < 12) {
            const int gh = gh0 + tid, ty = gh >> 5, h = gh & 31;
            const uint32_t m = ((const uint32_t*)(smem + G1_SMEM_RED))[tid];
            if (ty == 1) g_kmax2[mt * H_ + h] = __uint_as_float(m);
            if (ty == 2) g_vmax[mt * H_ + h] = m;
        }
    }
    if (tid < 12) asm volatile("cp.async.bulk.wait_group.read 0;" ::: "memory");
}

}

typedef CUresult (*EncodeFn)(CUtensorMap*, CUtensorMapDataType, cuuint32_t, void*, const cuuint64_t*, const cuuint64_t*, const cuuint32_t*,
                             const cuuint32_t*, CUtensorMapInterleave, CUtensorMapSwizzle, CUtensorMapL2promotion, CUtensorMapFloatOOBfill);
static void make_map(EncodeFn enc, CUtensorMap* tm, const void* base, uint64_t cols, uint64_t rows, uint32_t box_cols, uint32_t box_rows,
                     CUtensorMapSwizzle sw = CU_TENSOR_MAP_SWIZZLE_128B) {
    cuuint64_t dims[2] = {cols, rows}, strides[1] = {cols * 2};
    cuuint32_t box[2] = {box_cols, box_rows}, es[2] = {1, 1};
    enc(tm, CU_TENSOR_MAP_DATA_TYPE_BFLOAT16, 2, const_cast<void*>(base), dims, strides, box, es, CU_TENSOR_MAP_INTERLEAVE_NONE,
        sw, sw == CU_TENSOR_MAP_SWIZZLE_NONE ? CU_TENSOR_MAP_L2_PROMOTION_NONE : CU_TENSOR_MAP_L2_PROMOTION_L2_128B, CU_TENSOR_MAP_FLOAT_OOB_FILL_NONE);
}

extern "C" void kernel_launch(void* const* d_in, const int* in_sizes, int n_in, void* d_out, int out_size) {
    const __nv_bfloat16* x = (const __nv_bfloat16*)d_in[0];
    const __nv_bfloat16* wqkv = (const __nv_bfloat16*)d_in[1];
    const __nv_bfloat16* wo = (const __nv_bfloat16*)d_in[2];
    static EncodeFn enc = nullptr;
    static void *o_ptr = nullptr, *bt_ptr = nullptr;
    if (!enc) {
        void* fn = nullptr;
        cudaDriverEntryPointQueryResult qr;
        cudaGetDriverEntryPoint("cuTensorMapEncodeTiled", &fn, cudaEnableDefault, &qr);
        enc = (EncodeFn)fn;
        cudaGetSymbolAddress(&o_ptr, g_O);
        cudaGetSymbolAddress(&bt_ptr, g_bT);
        cudaFuncSetAttribute(attn_kernel, cudaFuncAttributeMaxDynamicSharedMemorySize, ATT_SMEM);
        cudaFuncSetAttribute(qkv_kernel, cudaFuncAttributeMaxDynamicSharedMemorySize, G1_SMEM);
    }
    CUtensorMap tmX, tmW, tmO, tmBT, tmU, tmOut;
    make_map(enc, &tmX, x, 576, 2048, 64, 128);
    make_map(enc, &tmW, wqkv, 1728, 576, 64, 64);
    make_map(enc, &tmO, o_ptr, 576, 2048, 64, 64);
    make_map(enc, &tmBT, bt_ptr, 2048, 576, 64, 144);
    make_map(enc, &tmOut, d_out, 576, 2048, 144, 64, CU_TENSOR_MAP_SWIZZLE_NONE);
    make_map(enc, &tmU, x, 576, 2048, 8, 256, CU_TENSOR_MAP_SWIZZLE_NONE);
    cudaStream_t st = cudaStreamPerThread;
    ConvParams cp{x, (const __nv_bfloat16*)d_in[4], (const __nv_bfloat16*)d_in[5], (const __nv_bfloat16*)d_in[6], (const __nv_bfloat16*)d_in[7],
                  (const __nv_bfloat16*)d_in[8], (const __nv_bfloat16*)d_in[9], (const __nv_bfloat16*)d_in[10], (const __nv_bfloat16*)d_in[11]};
    cudaLaunchAttribute pdl[1];
    pdl[0].id = cudaLaunchAttributeProgrammaticStreamSerialization;
    pdl[0].val.programmaticStreamSerializationAllowed = 1;
    auto cfg = [&](int grid, int block, int smem, bool dep) {
        cudaLaunchConfig_t c = {};
        c.gridDim = dim3(grid); c.blockDim = dim3(block); c.dynamicSmemBytes = smem; c.stream = st;
        if (dep) { c.attrs = pdl; c.numAttrs = 1; }
        return c;
    };
    cudaLaunchConfig_t c1 = cfg(132, 384, G1_SMEM, false), c2 = cfg(132, 512, ATT_SMEM, true);
    cudaLaunchKernelEx(&c1, qkv_kernel, tmX, tmW, tmU, cp, (const __nv_bfloat16*)d_in[12], wo);
    cudaLaunchKernelEx(&c2, attn_kernel, tmU, tmO, tmBT, tmOut, cp, wqkv);
}
```
